```python
import torch

def _softmax(x, axis=-1):
    return torch.softmax(x, dim=axis)
def _gelu(x):
    return torch.nn.functional.gelu(x, approximate="tanh")
def _silu(x):
    return torch.nn.functional.silu(x)
def _sigmoid(x):
    return torch.sigmoid(x)
def _layernorm(x, axis=-1, eps=1e-5):
    m = x.mean(dim=axis, keepdim=True)
    v = x.var(dim=axis, keepdim=True, unbiased=False)
    return (x - m) / torch.sqrt(v + eps)
def _scatter_add(tgt, idx, src, axis=0):
    return tgt.clone().index_add_(axis, idx, src)
def _segment_sum(src, seg, n):
    out = torch.zeros((n,) + src.shape[1:], dtype=src.dtype)
    return out.index_add_(0, seg, src)
def _pad(x, pw):
    flat = tuple(v for pair in reversed(pw) for v in pair)
    return torch.nn.functional.pad(x, flat)

kernel_name = 'parallel_sum__linear_attn_block__mixer_token_mlp__prompt'

def setup_inputs():

    _w = (lambda a: (lambda t: t.to(torch.bfloat16) if t.is_floating_point() else t)(torch.as_tensor(a)))
    def _A_setup():
        B, S, D = 1, 2048, 640
        return {
            "x": _w((lambda *s: torch.randn(*s, dtype=torch.bfloat16) * 0.05)(B, S, D)),
            "wqkv": _w((lambda *s: torch.randn(*s, dtype=torch.bfloat16) * 0.05)(D, 3 * D)),
            "wo": _w((lambda *s: torch.randn(*s, dtype=torch.bfloat16) * 0.05)(D, D)),
        }
    _A_in = _A_setup()

    def _B_setup():
        B, S, D, F = 1, 2048, 640, 1728
        return {
            "x": _w((lambda *s: torch.randn(*s, dtype=torch.bfloat16) * 0.05)(B, S, D)),
            "w1": _w((lambda *s: torch.randn(*s, dtype=torch.bfloat16) * 0.4)(S, F) * (S ** -0.5)),
            "b1": _w((lambda *s: torch.randn(*s, dtype=torch.bfloat16) * 3.2)(F) * 0.02),
            "w2": _w((lambda *s: torch.randn(*s, dtype=torch.bfloat16) * 0.2)(F, S) * (F ** -0.5)),
            "b2": _w((lambda *s: torch.randn(*s, dtype=torch.bfloat16) * 0.4)(S) * 0.02),
        }
    _B_in = _B_setup()

    return {
        "A_x": _A_in["x"],
        "A_wqkv": _A_in["wqkv"],
        "A_wo": _A_in["wo"],
        "B_x": _B_in["x"],
        "B_w1": _B_in["w1"],
        "B_b1": _B_in["b1"],
        "B_w2": _B_in["w2"],
        "B_b2": _B_in["b2"],
    }

def reference(A_x, A_wqkv, A_wo, B_x, B_w1, B_b1, B_w2, B_b2):
    def _A_ref(x, wqkv, wo):
        B, S, D = x.shape
        H = 32; Dh = D // H
        qkv = (lambda x, *d: x.permute(*d))((x @ wqkv).reshape(B, S, 3, H, Dh), 2, 0, 3, 1, 4)
        q, k, v = qkv[0], qkv[1], qkv[2]
        phi = lambda t: torch.where(t > 0, t + 1, torch.exp(t)) + 1e-6
        pq, pk = phi(q), phi(k)
        kv = torch.einsum("bhsd,bhse->bhde", pk, v)
        z = torch.einsum("bhsd->bhd", pk)
        num = torch.einsum("bhqd,bhde->bhqe", pq, kv)
        den = torch.einsum("bhqd,bhd->bhq", pq, z)[..., None] + 1e-6
        o = num / den
        return (lambda x, *d: x.permute(*d))(o, 0, 2, 1, 3).reshape(B, S, D) @ wo

    def _B_ref(x, w1, b1, w2, b2):
        B, S, D = x.shape
        h = _layernorm(x, axis=-1)
        u = torch.einsum("bsd,sf->bdf", h, w1) + b1
        u = _gelu(u)
        y = torch.einsum("bdf,fs->bds", u, w2) + b2
        return (lambda x, *d: x.permute(*d))(y, 0, 2, 1)

    x = A_x
    xn = _layernorm(x, axis=-1)
    return x + _A_ref(xn, A_wqkv, A_wo) + _B_ref(xn, B_w1, B_b1, B_w2, B_b2)
```

```cpp
#include <cuda_runtime.h>
#include <cuda_bf16.h>
#include <cuda.h>
#include <stdint.h>
__device__ __forceinline__ void wgmma_n160_t00(float (&d)[80], uint64_t da, uint64_t db, int scale_d) {
  asm volatile("{\n.reg .pred p;\nsetp.ne.b32 p, %82, 0;\n"
  "wgmma.mma_async.sync.aligned.m64n160k16.f32.bf16.bf16 "
  "{%0, %1, %2, %3, %4, %5, %6, %7, %8, %9, %10, %11, %12, %13, %14, %15, %16, %17, %18, %19, %20, %21, %22, %23, %24, %25, %26, %27, %28, %29, %30, %31, %32, %33, %34, %35, %36, %37, %38, %39, %40, %41, %42, %43, %44, %45, %46, %47, %48, %49, %50, %51, %52, %53, %54, %55, %56, %57, %58, %59, %60, %61, %62, %63, %64, %65, %66, %67, %68, %69, %70, %71, %72, %73, %74, %75, %76, %77, %78, %79}, "
  "%80, %81, p, 1, 1, 0, 0;\n}\n"
  : "+f"(d[0]), "+f"(d[1]), "+f"(d[2]), "+f"(d[3]), "+f"(d[4]), "+f"(d[5]), "+f"(d[6]), "+f"(d[7]), "+f"(d[8]), "+f"(d[9]), "+f"(d[10]), "+f"(d[11]), "+f"(d[12]), "+f"(d[13]), "+f"(d[14]), "+f"(d[15]), "+f"(d[16]), "+f"(d[17]), "+f"(d[18]), "+f"(d[19]), "+f"(d[20]), "+f"(d[21]), "+f"(d[22]), "+f"(d[23]), "+f"(d[24]), "+f"(d[25]), "+f"(d[26]), "+f"(d[27]), "+f"(d[28]), "+f"(d[29]), "+f"(d[30]), "+f"(d[31]), "+f"(d[32]), "+f"(d[33]), "+f"(d[34]), "+f"(d[35]), "+f"(d[36]), "+f"(d[37]), "+f"(d[38]), "+f"(d[39]), "+f"(d[40]), "+f"(d[41]), "+f"(d[42]), "+f"(d[43]), "+f"(d[44]), "+f"(d[45]), "+f"(d[46]), "+f"(d[47]), "+f"(d[48]), "+f"(d[49]), "+f"(d[50]), "+f"(d[51]), "+f"(d[52]), "+f"(d[53]), "+f"(d[54]), "+f"(d[55]), "+f"(d[56]), "+f"(d[57]), "+f"(d[58]), "+f"(d[59]), "+f"(d[60]), "+f"(d[61]), "+f"(d[62]), "+f"(d[63]), "+f"(d[64]), "+f"(d[65]), "+f"(d[66]), "+f"(d[67]), "+f"(d[68]), "+f"(d[69]), "+f"(d[70]), "+f"(d[71]), "+f"(d[72]), "+f"(d[73]), "+f"(d[74]), "+f"(d[75]), "+f"(d[76]), "+f"(d[77]), "+f"(d[78]), "+f"(d[79])
  : "l"(da), "l"(db), "r"(scale_d));
}
__device__ __forceinline__ void wgmma_n160_t01(float (&d)[80], uint64_t da, uint64_t db, int scale_d) {
  asm volatile("{\n.reg .pred p;\nsetp.ne.b32 p, %82, 0;\n"
  "wgmma.mma_async.sync.aligned.m64n160k16.f32.bf16.bf16 "
  "{%0, %1, %2, %3, %4, %5, %6, %7, %8, %9, %10, %11, %12, %13, %14, %15, %16, %17, %18, %19, %20, %21, %22, %23, %24, %25, %26, %27, %28, %29, %30, %31, %32, %33, %34, %35, %36, %37, %38, %39, %40, %41, %42, %43, %44, %45, %46, %47, %48, %49, %50, %51, %52, %53, %54, %55, %56, %57, %58, %59, %60, %61, %62, %63, %64, %65, %66, %67, %68, %69, %70, %71, %72, %73, %74, %75, %76, %77, %78, %79}, "
  "%80, %81, p, 1, 1, 0, 1;\n}\n"
  : "+f"(d[0]), "+f"(d[1]), "+f"(d[2]), "+f"(d[3]), "+f"(d[4]), "+f"(d[5]), "+f"(d[6]), "+f"(d[7]), "+f"(d[8]), "+f"(d[9]), "+f"(d[10]), "+f"(d[11]), "+f"(d[12]), "+f"(d[13]), "+f"(d[14]), "+f"(d[15]), "+f"(d[16]), "+f"(d[17]), "+f"(d[18]), "+f"(d[19]), "+f"(d[20]), "+f"(d[21]), "+f"(d[22]), "+f"(d[23]), "+f"(d[24]), "+f"(d[25]), "+f"(d[26]), "+f"(d[27]), "+f"(d[28]), "+f"(d[29]), "+f"(d[30]), "+f"(d[31]), "+f"(d[32]), "+f"(d[33]), "+f"(d[34]), "+f"(d[35]), "+f"(d[36]), "+f"(d[37]), "+f"(d[38]), "+f"(d[39]), "+f"(d[40]), "+f"(d[41]), "+f"(d[42]), "+f"(d[43]), "+f"(d[44]), "+f"(d[45]), "+f"(d[46]), "+f"(d[47]), "+f"(d[48]), "+f"(d[49]), "+f"(d[50]), "+f"(d[51]), "+f"(d[52]), "+f"(d[53]), "+f"(d[54]), "+f"(d[55]), "+f"(d[56]), "+f"(d[57]), "+f"(d[58]), "+f"(d[59]), "+f"(d[60]), "+f"(d[61]), "+f"(d[62]), "+f"(d[63]), "+f"(d[64]), "+f"(d[65]), "+f"(d[66]), "+f"(d[67]), "+f"(d[68]), "+f"(d[69]), "+f"(d[70]), "+f"(d[71]), "+f"(d[72]), "+f"(d[73]), "+f"(d[74]), "+f"(d[75]), "+f"(d[76]), "+f"(d[77]), "+f"(d[78]), "+f"(d[79])
  : "l"(da), "l"(db), "r"(scale_d));
}
__device__ __forceinline__ void wgmma_n160_t10(float (&d)[80], uint64_t da, uint64_t db, int scale_d) {
  asm volatile("{\n.reg .pred p;\nsetp.ne.b32 p, %82, 0;\n"
  "wgmma.mma_async.sync.aligned.m64n160k16.f32.bf16.bf16 "
  "{%0, %1, %2, %3, %4, %5, %6, %7, %8, %9, %10, %11, %12, %13, %14, %15, %16, %17, %18, %19, %20, %21, %22, %23, %24, %25, %26, %27, %28, %29, %30, %31, %32, %33, %34, %35, %36, %37, %38, %39, %40, %41, %42, %43, %44, %45, %46, %47, %48, %49, %50, %51, %52, %53, %54, %55, %56, %57, %58, %59, %60, %61, %62, %63, %64, %65, %66, %67, %68, %69, %70, %71, %72, %73, %74, %75, %76, %77, %78, %79}, "
  "%80, %81, p, 1, 1, 1, 0;\n}\n"
  : "+f"(d[0]), "+f"(d[1]), "+f"(d[2]), "+f"(d[3]), "+f"(d[4]), "+f"(d[5]), "+f"(d[6]), "+f"(d[7]), "+f"(d[8]), "+f"(d[9]), "+f"(d[10]), "+f"(d[11]), "+f"(d[12]), "+f"(d[13]), "+f"(d[14]), "+f"(d[15]), "+f"(d[16]), "+f"(d[17]), "+f"(d[18]), "+f"(d[19]), "+f"(d[20]), "+f"(d[21]), "+f"(d[22]), "+f"(d[23]), "+f"(d[24]), "+f"(d[25]), "+f"(d[26]), "+f"(d[27]), "+f"(d[28]), "+f"(d[29]), "+f"(d[30]), "+f"(d[31]), "+f"(d[32]), "+f"(d[33]), "+f"(d[34]), "+f"(d[35]), "+f"(d[36]), "+f"(d[37]), "+f"(d[38]), "+f"(d[39]), "+f"(d[40]), "+f"(d[41]), "+f"(d[42]), "+f"(d[43]), "+f"(d[44]), "+f"(d[45]), "+f"(d[46]), "+f"(d[47]), "+f"(d[48]), "+f"(d[49]), "+f"(d[50]), "+f"(d[51]), "+f"(d[52]), "+f"(d[53]), "+f"(d[54]), "+f"(d[55]), "+f"(d[56]), "+f"(d[57]), "+f"(d[58]), "+f"(d[59]), "+f"(d[60]), "+f"(d[61]), "+f"(d[62]), "+f"(d[63]), "+f"(d[64]), "+f"(d[65]), "+f"(d[66]), "+f"(d[67]), "+f"(d[68]), "+f"(d[69]), "+f"(d[70]), "+f"(d[71]), "+f"(d[72]), "+f"(d[73]), "+f"(d[74]), "+f"(d[75]), "+f"(d[76]), "+f"(d[77]), "+f"(d[78]), "+f"(d[79])
  : "l"(da), "l"(db), "r"(scale_d));
}
__device__ __forceinline__ void wgmma_n160_t11(float (&d)[80], uint64_t da, uint64_t db, int scale_d) {
  asm volatile("{\n.reg .pred p;\nsetp.ne.b32 p, %82, 0;\n"
  "wgmma.mma_async.sync.aligned.m64n160k16.f32.bf16.bf16 "
  "{%0, %1, %2, %3, %4, %5, %6, %7, %8, %9, %10, %11, %12, %13, %14, %15, %16, %17, %18, %19, %20, %21, %22, %23, %24, %25, %26, %27, %28, %29, %30, %31, %32, %33, %34, %35, %36, %37, %38, %39, %40, %41, %42, %43, %44, %45, %46, %47, %48, %49, %50, %51, %52, %53, %54, %55, %56, %57, %58, %59, %60, %61, %62, %63, %64, %65, %66, %67, %68, %69, %70, %71, %72, %73, %74, %75, %76, %77, %78, %79}, "
  "%80, %81, p, 1, 1, 1, 1;\n}\n"
  : "+f"(d[0]), "+f"(d[1]), "+f"(d[2]), "+f"(d[3]), "+f"(d[4]), "+f"(d[5]), "+f"(d[6]), "+f"(d[7]), "+f"(d[8]), "+f"(d[9]), "+f"(d[10]), "+f"(d[11]), "+f"(d[12]), "+f"(d[13]), "+f"(d[14]), "+f"(d[15]), "+f"(d[16]), "+f"(d[17]), "+f"(d[18]), "+f"(d[19]), "+f"(d[20]), "+f"(d[21]), "+f"(d[22]), "+f"(d[23]), "+f"(d[24]), "+f"(d[25]), "+f"(d[26]), "+f"(d[27]), "+f"(d[28]), "+f"(d[29]), "+f"(d[30]), "+f"(d[31]), "+f"(d[32]), "+f"(d[33]), "+f"(d[34]), "+f"(d[35]), "+f"(d[36]), "+f"(d[37]), "+f"(d[38]), "+f"(d[39]), "+f"(d[40]), "+f"(d[41]), "+f"(d[42]), "+f"(d[43]), "+f"(d[44]), "+f"(d[45]), "+f"(d[46]), "+f"(d[47]), "+f"(d[48]), "+f"(d[49]), "+f"(d[50]), "+f"(d[51]), "+f"(d[52]), "+f"(d[53]), "+f"(d[54]), "+f"(d[55]), "+f"(d[56]), "+f"(d[57]), "+f"(d[58]), "+f"(d[59]), "+f"(d[60]), "+f"(d[61]), "+f"(d[62]), "+f"(d[63]), "+f"(d[64]), "+f"(d[65]), "+f"(d[66]), "+f"(d[67]), "+f"(d[68]), "+f"(d[69]), "+f"(d[70]), "+f"(d[71]), "+f"(d[72]), "+f"(d[73]), "+f"(d[74]), "+f"(d[75]), "+f"(d[76]), "+f"(d[77]), "+f"(d[78]), "+f"(d[79])
  : "l"(da), "l"(db), "r"(scale_d));
}

typedef __nv_bfloat16 bf16;
constexpr int S_ = 2048, D_ = 640, F_ = 1728;

__device__ float2 g_stats[S_];
__device__ __align__(16) float g_csum[4 * 3 * D_];
__device__ __align__(1024) bf16 g_hT[D_ * S_];
__device__ __align__(1024) bf16 g_g[D_ * F_];
__device__ __align__(1024) bf16 g_pqn[S_ * D_];
__device__ __align__(1024) bf16 g_q[S_ * D_];
__device__ __align__(1024) float g_kvp[32 * 480];
__device__ __align__(1024) float g_part[64 * 20 * 256 * 4];
constexpr int C_Q1 = 176;
constexpr int C_KV = 32;
constexpr int C_Q = 36;
constexpr int C_G = 52;
constexpr int C_LN = 108;
constexpr int C_Y = 109;
constexpr int C_CSD = 174;
constexpr int C_DONE = 173;
constexpr int C_TOTAL = 240;
__device__ unsigned g_cnt[C_TOTAL];

__device__ __forceinline__ uint32_t smem_u32(const void* p) { return (uint32_t)__cvta_generic_to_shared(p); }
__device__ __forceinline__ void mbar_init(uint32_t bar, uint32_t cnt) { asm volatile("mbarrier.init.shared::cta.b64 [%0], %1;" ::"r"(bar), "r"(cnt)); }
__device__ __forceinline__ void mbar_expect_tx(uint32_t bar, uint32_t bytes) { asm volatile("mbarrier.arrive.expect_tx.shared::cta.b64 _, [%0], %1;" ::"r"(bar), "r"(bytes) : "memory"); }
__device__ __forceinline__ void mbar_arrive_cluster(uint32_t bar, uint32_t cta) {
  asm volatile("{\n.reg .b32 ra;\nmapa.shared::cluster.u32 ra, %0, %1;\nmbarrier.arrive.shared::cluster.b64 _, [ra];\n}\n" ::"r"(bar), "r"(cta) : "memory");
}
__device__ __forceinline__ void mbar_wait(uint32_t bar, uint32_t parity) {
  uint32_t ok;
  uint32_t spins = 0;
  do {
    asm volatile("{\n.reg .pred p;\nmbarrier.try_wait.parity.shared::cta.b64 p, [%1], %2;\nselp.u32 %0, 1, 0, p;\n}\n" : "=r"(ok) : "r"(bar), "r"(parity) : "memory");
  } while (!ok && ++spins < (1u << 22));
}
__device__ __forceinline__ void tma_2d(uint32_t dst, const CUtensorMap* tm, uint32_t bar, int c0, int c1) {
  asm volatile("cp.async.bulk.tensor.2d.shared::cluster.global.mbarrier::complete_tx::bytes [%0], [%1, {%3, %4}], [%2];"
               ::"r"(dst), "l"((uint64_t)tm), "r"(bar), "r"(c0), "r"(c1) : "memory");
}
__device__ __forceinline__ void tma_2d_mc(uint32_t dst, const CUtensorMap* tm, uint32_t bar, int c0, int c1) {
  asm volatile("cp.async.bulk.tensor.2d.shared::cluster.global.mbarrier::complete_tx::bytes.multicast::cluster [%0], [%1, {%3, %4}], [%2], %5;"
               ::"r"(dst), "l"((uint64_t)tm), "r"(bar), "r"(c0), "r"(c1), "h"((uint16_t)3) : "memory");
}
__device__ __forceinline__ void tma_3d(uint32_t dst, const CUtensorMap* tm, uint32_t bar, int c0, int c1, int c2) {
  asm volatile("cp.async.bulk.tensor.3d.shared::cluster.global.mbarrier::complete_tx::bytes [%0], [%1, {%3, %4, %5}], [%2];"
               ::"r"(dst), "l"((uint64_t)tm), "r"(bar), "r"(c0), "r"(c1), "r"(c2) : "memory");
}
__device__ __forceinline__ void ldsm_x4(uint32_t& r0, uint32_t& r1, uint32_t& r2, uint32_t& r3, uint32_t addr) {
  asm volatile("ldmatrix.sync.aligned.m8n8.x4.shared.b16 {%0,%1,%2,%3}, [%4];" : "=r"(r0), "=r"(r1), "=r"(r2), "=r"(r3) : "r"(addr) : "memory");
}
__device__ __forceinline__ void tma_3d_mc(uint32_t dst, const CUtensorMap* tm, uint32_t bar, int c0, int c1, int c2) {
  asm volatile("cp.async.bulk.tensor.3d.shared::cluster.global.mbarrier::complete_tx::bytes.multicast::cluster [%0], [%1, {%3, %4, %5}], [%2], %6;"
               ::"r"(dst), "l"((uint64_t)tm), "r"(bar), "r"(c0), "r"(c1), "r"(c2), "h"((uint16_t)3) : "memory");
}
__device__ __forceinline__ void tma_st_2d(const CUtensorMap* tm, uint32_t src, int c0, int c1) {
  asm volatile("cp.async.bulk.tensor.2d.global.shared::cta.bulk_group [%0, {%2, %3}], [%1];" ::"l"((uint64_t)tm), "r"(src), "r"(c0), "r"(c1) : "memory");
}
__device__ __forceinline__ void tma_st_3d(const CUtensorMap* tm, uint32_t src, int c0, int c1, int c2) {
  asm volatile("cp.async.bulk.tensor.3d.global.shared::cta.bulk_group [%0, {%2, %3, %4}], [%1];" ::"l"((uint64_t)tm), "r"(src), "r"(c0), "r"(c1), "r"(c2) : "memory");
}
__device__ __forceinline__ void bulk_commit_wait() { asm volatile("cp.async.bulk.commit_group;\ncp.async.bulk.wait_group 0;" ::: "memory"); }
__device__ __forceinline__ void bar_arrive(int id, int n) { asm volatile("bar.arrive %0, %1;" ::"r"(id), "r"(n) : "memory"); }
__device__ __forceinline__ uint64_t make_desc(uint32_t addr, uint32_t lbo, uint32_t sbo, uint64_t swz) {
  return (uint64_t)((addr & 0x3FFFF) >> 4) | ((uint64_t)(lbo >> 4) << 16) | ((uint64_t)(sbo >> 4) << 32) | (swz << 62);
}
__device__ __forceinline__ void wg_fence() { asm volatile("wgmma.fence.sync.aligned;" ::: "memory"); }
__device__ __forceinline__ void wg_commit() { asm volatile("wgmma.commit_group.sync.aligned;" ::: "memory"); }
template <int N> __device__ __forceinline__ void wg_wait() { asm volatile("wgmma.wait_group.sync.aligned %0;" ::"n"(N) : "memory"); }
__device__ __forceinline__ void bar_sync(int id, int n) { asm volatile("bar.sync %0, %1;" ::"r"(id), "r"(n) : "memory"); }
__device__ __forceinline__ void fence_proxy_async() { asm volatile("fence.proxy.async.global;" ::: "memory"); }
__device__ __forceinline__ void fence_proxy_smem() { asm volatile("fence.proxy.async.shared::cta;" ::: "memory"); }
__device__ __forceinline__ unsigned ld_acquire(const unsigned* p) {
  unsigned v; asm volatile("ld.acquire.gpu.global.u32 %0, [%1];" : "=r"(v) : "l"(p) : "memory"); return v;
}
__device__ __forceinline__ unsigned ld_relaxed(const unsigned* p) {
  unsigned v; asm volatile("ld.relaxed.gpu.global.u32 %0, [%1];" : "=r"(v) : "l"(p) : "memory"); return v;
}
__device__ __forceinline__ void wait_cnt(const unsigned* p, unsigned target) {
  uint32_t spins = 0;
  while (ld_relaxed(p) < target && ++spins < (1u << 22)) {}
}
__device__ __forceinline__ void signal_cnt(unsigned* p) {
  asm volatile("red.release.gpu.global.add.u32 [%0], 1;" ::"l"(p) : "memory");
}
__device__ __forceinline__ void signal_relaxed(unsigned* p) {
  asm volatile("red.relaxed.gpu.global.add.u32 [%0], 1;" ::"l"(p) : "memory");
}
__device__ __forceinline__ uint32_t pack_bf16(float lo, float hi) {
  uint32_t r; asm("cvt.rn.bf16x2.f32 %0, %1, %2;" : "=r"(r) : "f"(hi), "f"(lo)); return r;
}
__device__ __forceinline__ float bf_lo(uint32_t v) { return __uint_as_float(v << 16); }
__device__ __forceinline__ float bf_hi(uint32_t v) { return __uint_as_float(v & 0xffff0000u); }
__device__ __forceinline__ void ldsm_x4_t(uint32_t& r0, uint32_t& r1, uint32_t& r2, uint32_t& r3, uint32_t addr) {
  asm volatile("ldmatrix.sync.aligned.m8n8.x4.trans.shared.b16 {%0,%1,%2,%3}, [%4];" : "=r"(r0), "=r"(r1), "=r"(r2), "=r"(r3) : "r"(addr) : "memory");
}
__device__ __forceinline__ void ldsm_x2_t(uint32_t& r0, uint32_t& r1, uint32_t addr) {
  asm volatile("ldmatrix.sync.aligned.m8n8.x2.trans.shared.b16 {%0,%1}, [%2];" : "=r"(r0), "=r"(r1) : "r"(addr) : "memory");
}
__device__ __forceinline__ void stsm_x4_t(uint32_t addr, uint32_t r0, uint32_t r1, uint32_t r2, uint32_t r3) {
  asm volatile("stmatrix.sync.aligned.m8n8.x4.trans.shared.b16 [%0], {%1,%2,%3,%4};" ::"r"(addr), "r"(r0), "r"(r1), "r"(r2), "r"(r3) : "memory");
}
__device__ __forceinline__ void stsm_x4(uint32_t addr, uint32_t r0, uint32_t r1, uint32_t r2, uint32_t r3) {
  asm volatile("stmatrix.sync.aligned.m8n8.x4.shared.b16 [%0], {%1,%2,%3,%4};" ::"r"(addr), "r"(r0), "r"(r1), "r"(r2), "r"(r3) : "memory");
}
__device__ __forceinline__ void mma_16816(float (&c)[4], uint32_t a0, uint32_t a1, uint32_t a2, uint32_t a3, uint32_t b0, uint32_t b1) {
  asm volatile("mma.sync.aligned.m16n8k16.row.col.f32.bf16.bf16.f32 {%0,%1,%2,%3}, {%4,%5,%6,%7}, {%8,%9}, {%0,%1,%2,%3};"
               : "+f"(c[0]), "+f"(c[1]), "+f"(c[2]), "+f"(c[3]) : "r"(a0), "r"(a1), "r"(a2), "r"(a3), "r"(b0), "r"(b1));
}
__device__ __forceinline__ void sts32(uint32_t addr, uint32_t v) { asm volatile("st.shared.b32 [%0], %1;" ::"r"(addr), "r"(v) : "memory"); }
__device__ __forceinline__ uint32_t lds32(uint32_t addr) { uint32_t v; asm volatile("ld.shared.b32 %0, [%1];" : "=r"(v) : "r"(addr) : "memory"); return v; }
__device__ __forceinline__ uint4 lds128(uint32_t addr) { uint4 v; asm volatile("ld.shared.v4.b32 {%0,%1,%2,%3}, [%4];" : "=r"(v.x), "=r"(v.y), "=r"(v.z), "=r"(v.w) : "r"(addr) : "memory"); return v; }
__device__ __forceinline__ void sts128(uint32_t addr, uint4 v) { asm volatile("st.shared.v4.b32 [%0], {%1,%2,%3,%4};" ::"r"(addr), "r"(v.x), "r"(v.y), "r"(v.z), "r"(v.w) : "memory"); }
__device__ __forceinline__ float phi_fn(float t) {
  float e; asm("ex2.approx.ftz.f32 %0, %1;" : "=f"(e) : "f"(t * 1.4426950408889634f));
  return (t > 0.f ? t + 1.f : e) + 1e-6f;
}
__device__ __forceinline__ uint32_t phi2(uint32_t v) { return pack_bf16(phi_fn(bf_lo(v)), phi_fn(bf_hi(v))); }
__device__ __forceinline__ void mbar_arrive(uint32_t bar) { asm volatile("mbarrier.arrive.shared::cta.b64 _, [%0];" ::"r"(bar) : "memory"); }
__device__ __forceinline__ uint2 lds64(uint32_t addr) { uint2 v; asm volatile("ld.shared.v2.b32 {%0,%1}, [%2];" : "=r"(v.x), "=r"(v.y) : "r"(addr) : "memory"); return v; }
__device__ __forceinline__ float4 lds128f(uint32_t addr) { float4 v; asm volatile("ld.shared.v4.f32 {%0,%1,%2,%3}, [%4];" : "=f"(v.x), "=f"(v.y), "=f"(v.z), "=f"(v.w) : "r"(addr) : "memory"); return v; }
__device__ __forceinline__ float gelu_fn(float x) {
  const float y = x * fmaf(0.7978845608028654f * 0.044715f, x * x, 0.7978845608028654f);
  float th; asm("tanh.approx.f32 %0, %1;" : "=f"(th) : "f"(y));
  const float hx = 0.5f * x;
  return fmaf(hx, th, hx);
}
__device__ __forceinline__ void red_add_v2(float* p, float a, float b) {
  asm volatile("red.global.add.v2.f32 [%0], {%1, %2};" ::"l"(p), "f"(a), "f"(b) : "memory");
}

constexpr int ST36 = 5, SZ36 = 36864;
constexpr int ST56 = 3, SZ56 = 57344;
constexpr int OFF_STAGE = 184320;
constexpr int OFF_QT = 0;
constexpr int OFF_KVF = 147456;
constexpr int OFF_TAB = OFF_KVF + 15360;
constexpr int OFF_STAGE_KV2 = 118784;
constexpr int OFF_STAGE_KV = 172032;
constexpr int OFF_MISC = 225280;
constexpr int OFF_BARS = OFF_MISC;
constexpr int OFF_ZS = OFF_MISC + 256;
constexpr int OFF_CS = OFF_ZS + 640;
constexpr int OFF_ST = OFF_CS + 1920;
constexpr int SMEM_USED = OFF_MISC + 256 + 640 + 1920 + 1024;
constexpr int SMEM_BYTES = SMEM_USED + 1024;

struct Ptrs { const bf16* wqkv; const bf16* x; const bf16* wo; const bf16* b1; const bf16* b2; bf16* out; const bf16* w1; const bf16* w2; };

struct Ring { int s; uint32_t ph; };

__device__ __forceinline__ void release_stage(uint32_t bar) { mbar_arrive_cluster(bar, 0); mbar_arrive_cluster(bar, 1); }

template <int MODE>
__device__ __forceinline__ void mainloop36(float (&acc)[80], int nblk, Ring& r, int nst, uint32_t sb, int wg, bool zero_first, bool elect, bool last = false) {
  const uint32_t fullb = sb + OFF_BARS, emptyb = sb + OFF_BARS + 8 * ST36;
  int prev = 0;
#pragma unroll 1
  for (int kb = 0; kb < nblk; kb++) {
    const int s = r.s;
    mbar_wait(fullb + 8 * s, (r.ph >> s) & 1);
    r.ph ^= 1u << s;
    r.s = (s + 1 == nst) ? 0 : s + 1;
    const uint32_t sa = sb + s * SZ36 + wg * 8192, sbb = sb + s * SZ36 + 16384;
    const uint64_t da = (MODE == 0 || MODE == 3) ? make_desc(sa, 8192, 1024, 1) : make_desc(sa, 16, 1024, 1);
    const uint64_t db = (MODE >= 2) ? make_desc(sbb, 4096, 512, 2) : make_desc(sbb, 16, 1024, 1);
    wg_fence();
#pragma unroll
    for (int k = 0; k < 4; k++) {
      const int sc = (zero_first && kb == 0 && k == 0) ? 0 : 1;
      if (MODE == 0) wgmma_n160_t10(acc, da + k * 128, db + k * 2, sc);
      if (MODE == 1) wgmma_n160_t00(acc, da + k * 2, db + k * 2, sc);
      if (MODE == 2) wgmma_n160_t01(acc, da + k * 2, db + k * 64, sc);
      if (MODE == 3) wgmma_n160_t11(acc, da + k * 128, db + k * 64, sc);
    }
    wg_commit();
    if (kb > 0) {
      wg_wait<1>();
      if (elect && !(last && kb - 1 >= nblk - nst)) release_stage(emptyb + 8 * prev);
    }
    prev = s;
  }
  wg_wait<0>();
  if (elect && !last) release_stage(emptyb + 8 * prev);
}

__device__ __forceinline__ void dump_rowmajor(const float (&acc)[80], uint32_t stgw, int ww, int lane) {
  const int mi = lane >> 3, mr = lane & 7;
  const int row = ww * 16 + (mi & 1) * 8 + mr;
  const int sw = (row >> 1) & 3;
#pragma unroll
  for (int j = 0; j < 20; j += 2) {
    const int jb = j + (mi >> 1);
    const uint32_t addr = stgw + (j >> 2) * 4096 + row * 64 + ((((j & 3) + (mi >> 1)) ^ sw) << 4);
    (void)jb;
    stsm_x4(addr, pack_bf16(acc[4 * j], acc[4 * j + 1]), pack_bf16(acc[4 * j + 2], acc[4 * j + 3]),
            pack_bf16(acc[4 * j + 4], acc[4 * j + 5]), pack_bf16(acc[4 * j + 6], acc[4 * j + 7]));
  }
}

__global__ void __launch_bounds__(384, 1)
mega_kernel(const __grid_constant__ CUtensorMap tm_xn, const __grid_constant__ CUtensorMap tm_w5, const __grid_constant__ CUtensorMap tm_w1g,
            const __grid_constant__ CUtensorMap tm_w1, const __grid_constant__ CUtensorMap tm_hT, const __grid_constant__ CUtensorMap tm_w2,
            const __grid_constant__ CUtensorMap tm_g, const __grid_constant__ CUtensorMap tm_pqn, const __grid_constant__ CUtensorMap tm_MT,
            const __grid_constant__ CUtensorMap tm_pqs, const __grid_constant__ CUtensorMap tm_out, const __grid_constant__ CUtensorMap tm_xt,
            const __grid_constant__ CUtensorMap tm_qs, const Ptrs p) {
  extern __shared__ uint8_t smem_raw[];
  const uint32_t sb = (smem_u32(smem_raw) + 1023) & ~1023u;
  uint8_t* sgen = smem_raw + (sb - smem_u32(smem_raw));
  const int tid = threadIdx.x, warp = tid >> 5, lane = tid & 31;
  const int pair = blockIdx.x >> 1;
  const int rank = blockIdx.x & 1;
  const uint32_t full36 = sb + OFF_BARS, empty36 = full36 + 8 * ST36, full56 = empty36 + 8 * ST36, empty56 = full56 + 8 * ST56;
  const uint32_t zbar = empty56 + 8 * ST56;
  const uint32_t sfree = zbar + 8;
  const uint32_t abar = sfree + 16;
  const uint32_t xbar = abar + 8;
  const uint32_t qbar = xbar + 16;

  if (tid == 0) {
    for (int s = 0; s < ST36; s++) { mbar_init(full36 + 8 * s, 1); mbar_init(empty36 + 8 * s, 4); }
    for (int s = 0; s < ST56; s++) { mbar_init(full56 + 8 * s, 1); mbar_init(empty56 + 8 * s, 4); }
    mbar_init(zbar, 64);
    mbar_init(sfree, 1); mbar_init(sfree + 8, 1);
    mbar_init(abar, 64); mbar_init(xbar, 1); mbar_init(xbar + 8, 1); mbar_init(qbar, 1); mbar_init(qbar + 8, 1);
    asm volatile("fence.mbarrier_init.release.cluster;" ::: "memory");
  }
  __syncthreads();
  asm volatile("barrier.cluster.arrive.release.aligned;\nbarrier.cluster.wait.acquire.aligned;" ::: "memory");

  const bool roleU = pair < 28, roleK = (pair >= 28 && pair < 60), fin = pair < 64, roleQ = fin && !roleK;
  const int u_fi = 2 * (pair % 7) + rank, u_dj = pair / 7;
  const int f_q = roleK ? pair - 28 : (pair < 28 ? pair : pair - 32);
  const int f_si = 2 * (f_q & 7) + rank, f_dj = f_q >> 3;
#define XBV 14
  constexpr int XB = XBV;

  if (warp < 4) {
    asm volatile("setmaxnreg.dec.sync.aligned.u32 56;");
    if (warp == 0 && blockIdx.x < 128) bar_sync(6, 288);
    if (tid == 0) {
      Ring r = {0, 0};
      auto acquire36 = [&]() -> int {
        const int s = r.s;
        mbar_wait(empty36 + 8 * s, ((r.ph >> s) & 1) ^ 1);
        r.ph ^= 1u << s;
        r.s = (s + 1 == ST36) ? 0 : s + 1;
        mbar_expect_tx(full36 + 8 * s, SZ36);
        return s;
      };
      const int g0 = rank ? 3 : 0, g1 = rank ? 5 : 3;
      if (roleQ) {
#pragma unroll 1
        for (int kb = 0; kb < 10; kb++) {
          const int s = acquire36();
          const uint32_t fb = full36 + 8 * s, dst = sb + s * SZ36;
#pragma unroll 1
          for (int gq = g0; gq < g1; gq++) tma_3d_mc(dst + 16384 + gq * 4096, &tm_w1g, fb, 0, kb * 64, f_dj * 5 + gq);
          tma_2d(dst, &tm_xn, fb, kb * 64, f_si * 128);
        }
        if (roleU) {
#pragma unroll 1
          for (int kb = 0; kb < 32; kb++) {
            const int s = acquire36();
            const uint32_t fb = full36 + 8 * s, dst = sb + s * SZ36;
            tma_2d(dst, &tm_w1, fb, u_fi * 128, kb * 64);
            tma_2d(dst + 8192, &tm_w1, fb, u_fi * 128 + 64, kb * 64);
            if (kb == 0) { wait_cnt(&g_cnt[C_LN], 128); fence_proxy_async(); }
            tma_2d_mc(dst + 16384 + rank * 10240, &tm_hT, fb, kb * 64, u_dj * 160 + rank * 80);
          }
        }
      } else if (roleK) {
#pragma unroll 1
        for (int kb = 0; kb < 10; kb++) {
          const int s = kb % ST56; const uint32_t ph = (kb / ST56) & 1;
          mbar_wait(empty56 + 8 * s, ph ^ 1);
          mbar_expect_tx(full56 + 8 * s, SZ56);
          const uint32_t fb = full56 + 8 * s, dst = sb + s * SZ56;
          tma_3d_mc(dst + 16384 + rank * 20480, &tm_w5, fb, 0, kb * 64, 20 + rank * 20 + f_dj * 5);
          tma_2d(dst, &tm_xn, fb, kb * 64, f_si * 128);
        }
        mbar_wait(empty56 + 8 * 1, 0);
        mbar_wait(empty56 + 8 * 2, 0);
        mbar_wait(empty56 + 8 * 0, 1);
        r.ph ^= 0x1fu;
        wait_cnt(&g_cnt[C_Q1 + f_si * 4 + f_dj], 2);
        fence_proxy_async();
#pragma unroll
        for (int w = 0; w < 2; w++) {
          mbar_expect_tx(qbar + 8 * w, 20480);
          tma_3d(sb + OFF_QT + w * 20480, &tm_qs, qbar + 8 * w, 0, f_si * 128 + w * 64, f_dj * 5);
        }
#pragma unroll 1
        for (int kb = 0; kb < 10; kb++) {
          const int s = acquire36();
          const uint32_t fb = full36 + 8 * s, dst = sb + s * SZ36;
#pragma unroll 1
          for (int gq = g0; gq < g1; gq++) tma_3d_mc(dst + 16384 + gq * 4096, &tm_MT, fb, 0, kb * 64, f_dj * 5 + gq);
          if (kb == 0) { wait_cnt(&g_cnt[C_Q + f_si], 8); fence_proxy_async(); }
          tma_2d(dst, &tm_pqn, fb, kb * 64, f_si * 128);
        }
      }
      if (fin) {
        const int kb0 = roleK ? 0 : XB, kb1 = roleK ? XB : 27;
#pragma unroll 1
        for (int kb = kb0; kb < kb1; kb++) {
          const int s = acquire36();
          const uint32_t fb = full36 + 8 * s, dst = sb + s * SZ36;
          tma_2d(dst, &tm_w2, fb, f_si * 128, kb * 64);
          tma_2d(dst + 8192, &tm_w2, fb, f_si * 128 + 64, kb * 64);
          if (kb == kb0) { wait_cnt(&g_cnt[C_G + f_dj], 28); fence_proxy_async(); }
          tma_2d_mc(dst + 16384 + rank * 10240, &tm_g, fb, kb * 64, f_dj * 160 + rank * 80);
        }
      }
    } else if (warp == 3 && pair >= 64) {
      if (lane == 0) wait_cnt(&g_cnt[C_LN], 128);
      __syncwarp();
      const int sidx = (pair - 64) * 2 + rank;
      const char* w2b = (const char*)p.w2;
      const int chunk = 16384; const int nch = (S_ * F_ * 2) / chunk;
      for (int c = sidx * 32 + lane; c < nch; c += 4 * 32)
        asm volatile("cp.async.bulk.prefetch.L2.global [%0], %1;" ::"l"(w2b + (size_t)c * chunk), "r"(chunk) : "memory");
    }
    if (warp == 1 && blockIdx.x < 128) {
      bar_sync(4, 288);
      if (lane == 0) signal_cnt(&g_cnt[C_LN]);
    }
    if (warp >= 2 && fin) {
      if (lane == 0) wait_cnt(&g_cnt[C_LN], 128);
      __syncwarp();
      float* cs = (float*)(sgen + OFF_CS);
      float2* st = (float2*)(sgen + OFF_ST);
      const int at = tid - 64;
      float a[4][5]; float2 sv[2];
#pragma unroll
      for (int i = 0; i < 5; i++) {
        const int c = at + 64 * i;
        const float* q = g_csum + (roleK ? (c < 160 ? 640 : 1280 - 160) : 0) + f_dj * 160 + (roleK ? c : c % 160);
#pragma unroll
        for (int rp = 0; rp < 4; rp++) a[rp][i] = __ldcg(q + rp * (3 * D_));
      }
#pragma unroll
      for (int i = 0; i < 2; i++) sv[i] = __ldcg(g_stats + f_si * 128 + at + 64 * i);
#pragma unroll
      for (int i = 0; i < 5; i++) cs[at + 64 * i] = (a[0][i] + a[1][i]) + (a[2][i] + a[3][i]);
#pragma unroll
      for (int i = 0; i < 2; i++) st[at + 64 * i] = sv[i];
      mbar_arrive(abar);
      __syncwarp();
      if (!roleK && lane == 0) signal_cnt(&g_cnt[C_CSD]);
    }
    if (warp == 1 && roleK) {
      bar_sync(5, 288);
      if (lane == 0) signal_cnt(&g_cnt[C_KV + f_dj]);
      __syncwarp();
    }
    if (warp >= 2 && roleK) {
      const int at = tid - 64;
      if (lane == 0) wait_cnt(&g_cnt[C_KV + f_dj], 16);
      __syncwarp();
      float4 v[15];
      const float4* src4 = (const float4*)(g_kvp + (size_t)f_dj * 8 * 480);
#pragma unroll
      for (int i = 0; i < 15; i++) v[i] = __ldcg(src4 + at + 64 * i);
#pragma unroll
      for (int i = 0; i < 15; i++) ((float4*)(sgen + OFF_KVF))[at + 64 * i] = v[i];
      mbar_arrive(zbar);
    }
    if (warp == 1 || warp == 2) {
      const int w = warp - 1;
      const uint32_t stgw = sb + OFF_STAGE + w * 20480;
      if (roleQ) {
        bar_sync(2 + w, 160);
        if (lane == 0) {
          tma_st_3d(&tm_qs, stgw, 0, f_si * 128 + w * 64, f_dj * 5);
          bulk_commit_wait();
          fence_proxy_async();
          signal_relaxed(&g_cnt[C_Q1 + f_si * 4 + f_dj]);
          mbar_arrive(sfree + 8 * w);
        }
        if (roleU) {
          bar_sync(2 + w, 160);
          if (lane == 0) {
            if (u_fi * 128 + w * 64 < F_) {
              tma_st_2d(&tm_g, stgw, u_fi * 128 + w * 64, u_dj * 160);
              tma_st_2d(&tm_g, stgw + 10240, u_fi * 128 + w * 64, u_dj * 160 + 80);
            }
            bulk_commit_wait();
            fence_proxy_async();
            signal_relaxed(&g_cnt[C_G + u_dj]);
          }
        }
      } else if (roleK) {
        bar_sync(2 + w, 160);
        if (lane == 0) {
          tma_st_3d(&tm_pqs, stgw, 0, f_si * 128 + w * 64, f_dj * 5);
          bulk_commit_wait();
          fence_proxy_async();
          signal_relaxed(&g_cnt[C_Q + f_si]);
          mbar_expect_tx(xbar + 8 * w, 20480);
          tma_3d(stgw, &tm_xt, xbar + 8 * w, 0, f_si * 128 + w * 64, f_dj * 5);
        }
        bar_sync(2 + w, 160);
        if (lane == 0) {
          tma_st_3d(&tm_out, stgw, 0, f_si * 128 + w * 64, f_dj * 5);
          bulk_commit_wait();
        }
      }
    }
  } else {
    asm volatile("setmaxnreg.inc.sync.aligned.u32 224;");
    const int ct = tid - 128;
    const int cw = ct >> 5;
    const int wg = cw >> 2, ww = cw & 3;
    const int g = lane >> 2, t = lane & 3;
    const bool elect = (ct & 127) == 0;
    Ring r = {0, 0};
    const uint32_t stg = sb + OFF_STAGE;
    if (blockIdx.x < 128) {
      const int row0 = blockIdx.x * 16;
      const bool has3 = lane < 16;
      uint32_t pk[2][12];
#pragma unroll
      for (int rr = 0; rr < 2; rr++) {
        const bf16* xr = p.x + (size_t)(row0 + cw * 2 + rr) * D_;
        const uint4 a = *(const uint4*)(xr + lane * 8), b = *(const uint4*)(xr + 256 + lane * 8);
        const uint4 c = has3 ? *(const uint4*)(xr + 512 + lane * 8) : make_uint4(0, 0, 0, 0);
        pk[rr][0] = a.x; pk[rr][1] = a.y; pk[rr][2] = a.z; pk[rr][3] = a.w; pk[rr][4] = b.x; pk[rr][5] = b.y; pk[rr][6] = b.z; pk[rr][7] = b.w;
        pk[rr][8] = c.x; pk[rr][9] = c.y; pk[rr][10] = c.z; pk[rr][11] = c.w;
      }
      if (ct < 120) g_kvp[blockIdx.x * 120 + ct] = 0.f;
      uint4 wv[5];
#pragma unroll
      for (int i = 0; i < 5; i++) wv[i] = (ct < 240) ? *(const uint4*)(p.wqkv + (size_t)(blockIdx.x * 5 + i) * (3 * D_) + ct * 8) : make_uint4(0, 0, 0, 0);
      if (ct < 240) {
        float a8[8];
#pragma unroll
        for (int i = 0; i < 8; i++) a8[i] = 0.f;
#pragma unroll
        for (int i = 0; i < 5; i++) {
          a8[0] += bf_lo(wv[i].x); a8[1] += bf_hi(wv[i].x); a8[2] += bf_lo(wv[i].y); a8[3] += bf_hi(wv[i].y);
          a8[4] += bf_lo(wv[i].z); a8[5] += bf_hi(wv[i].z); a8[6] += bf_lo(wv[i].w); a8[7] += bf_hi(wv[i].w);
        }
        float* o = g_csum + (blockIdx.x & 3) * (3 * D_) + ct * 8;
        asm volatile("red.global.add.v4.f32 [%0], {%1, %2, %3, %4};" ::"l"(o), "f"(a8[0]), "f"(a8[1]), "f"(a8[2]), "f"(a8[3]) : "memory");
        asm volatile("red.global.add.v4.f32 [%0], {%1, %2, %3, %4};" ::"l"(o + 4), "f"(a8[4]), "f"(a8[5]), "f"(a8[6]), "f"(a8[7]) : "memory");
      }
      {
        uint32_t chk = 0;
#pragma unroll
        for (int rr = 0; rr < 2; rr++)
#pragma unroll
          for (int i = 0; i < 12; i += 4) chk |= pk[rr][i];
        asm volatile("" ::"r"(chk) : "memory");
        bar_arrive(6, 288);
      }
#pragma unroll
      for (int pass = 0; pass < 2; pass++) {
        float s[2], q[2], piv[2];
#pragma unroll
        for (int rr = 0; rr < 2; rr++) {
          piv[rr] = (pass == 0) ? __shfl_sync(0xffffffffu, bf_lo(pk[rr][0]), 0) : 0.f;
          s[rr] = 0.f; q[rr] = 0.f;
#pragma unroll
          for (int i = 0; i < 12; i++) {
            if (i < 8 || has3) {
              const float a = bf_lo(pk[rr][i]) - piv[rr], b = bf_hi(pk[rr][i]) - piv[rr];
              s[rr] += a + b; q[rr] = fmaf(a, a, fmaf(b, b, q[rr]));
            }
          }
        }
#pragma unroll
        for (int o = 16; o > 0; o >>= 1) {
#pragma unroll
          for (int rr = 0; rr < 2; rr++) { s[rr] += __shfl_xor_sync(0xffffffffu, s[rr], o); q[rr] += __shfl_xor_sync(0xffffffffu, q[rr], o); }
        }
#pragma unroll
        for (int rr = 0; rr < 2; rr++) {
          const float ms = s[rr] * (1.f / 640.f);
          const float var = fmaxf(q[rr] * (1.f / 640.f) - ms * ms, 0.f);
          const float rs = rsqrtf(var + 1e-5f);
          const float mean = ms + piv[rr];
          const float mr = -mean * rs;
#pragma unroll
          for (int i = 0; i < 12; i++) pk[rr][i] = pack_bf16(fmaf(bf_lo(pk[rr][i]), rs, mr), fmaf(bf_hi(pk[rr][i]), rs, mr));
          if (pass == 0) {
            if (lane == 0) g_stats[row0 + cw * 2 + rr] = make_float2(mean, rs);
          } else {
            const uint32_t ha = stg + (cw * 2 + rr) * 1296;
            sts128(ha + lane * 16, make_uint4(pk[rr][0], pk[rr][1], pk[rr][2], pk[rr][3]));
            sts128(ha + 512 + lane * 16, make_uint4(pk[rr][4], pk[rr][5], pk[rr][6], pk[rr][7]));
            if (has3) sts128(ha + 1024 + lane * 16, make_uint4(pk[rr][8], pk[rr][9], pk[rr][10], pk[rr][11]));
          }
        }
      }
      bar_sync(1, 256);
#pragma unroll
      for (int k3 = 0; k3 < 3; k3++) {
        const int it = ct + 256 * k3;
        if (it < 640) {
          const int dp = it >> 1, hf = it & 1;
          uint32_t w[8];
#pragma unroll
          for (int i = 0; i < 8; i++) w[i] = lds32(stg + (hf * 8 + i) * 1296 + dp * 4);
          bf16* o0 = g_hT + (size_t)(2 * dp) * S_ + row0 + hf * 8;
          *(uint4*)(o0) = make_uint4(__byte_perm(w[0], w[1], 0x5410), __byte_perm(w[2], w[3], 0x5410), __byte_perm(w[4], w[5], 0x5410), __byte_perm(w[6], w[7], 0x5410));
          *(uint4*)(o0 + S_) = make_uint4(__byte_perm(w[0], w[1], 0x7632), __byte_perm(w[2], w[3], 0x7632), __byte_perm(w[4], w[5], 0x7632), __byte_perm(w[6], w[7], 0x7632));
        }
      }
      bar_arrive(4, 288);
    }

    if (roleQ) {
      {
        float acc[80];
        mainloop36<2>(acc, 10, r, ST36, sb, wg, true, elect);
        mbar_wait(abar, 0);
        {
          const float2 stA = *(const float2*)(sgen + OFF_ST + (wg * 64 + ww * 16 + g) * 8), stB = *(const float2*)(sgen + OFF_ST + (wg * 64 + ww * 16 + g + 8) * 8);
          const float* cs = (const float*)(sgen + OFF_CS) + 2 * t;
#pragma unroll
          for (int j = 0; j < 20; j++) {
            const float2 c = *(const float2*)(cs + 8 * j);
            acc[4 * j] = (acc[4 * j] - stA.x * c.x) * stA.y; acc[4 * j + 1] = (acc[4 * j + 1] - stA.x * c.y) * stA.y;
            acc[4 * j + 2] = (acc[4 * j + 2] - stB.x * c.x) * stB.y; acc[4 * j + 3] = (acc[4 * j + 3] - stB.x * c.y) * stB.y;
          }
        }
        bar_sync(1, 256);
        dump_rowmajor(acc, stg + wg * 20480, ww, lane);
        fence_proxy_smem();
        bar_arrive(2 + wg, 160);
      }
      if (roleU) {
        const int f0 = u_fi * 128 + wg * 64 + ww * 16 + g;
        const float bA = (f0 < F_) ? __bfloat162float(p.b1[f0]) : 0.f;
        const float bB = (f0 + 8 < F_) ? __bfloat162float(p.b1[f0 + 8]) : 0.f;
        float acc[80];
        mainloop36<0>(acc, 32, r, ST36, sb, wg, true, elect);
        mbar_wait(sfree + 8 * wg, 0);
        const int mi = lane >> 3, mr = lane & 7;
        const uint32_t base = stg + wg * 20480 + ((mi >> 1) * 8 + mr) * 128 + (((ww * 2 + (mi & 1)) ^ mr) << 4);
#pragma unroll
        for (int j = 0; j < 20; j += 2)
          stsm_x4_t(base + j * 8 * 128, pack_bf16(gelu_fn(acc[4 * j] + bA), gelu_fn(acc[4 * j + 1] + bA)), pack_bf16(gelu_fn(acc[4 * j + 2] + bB), gelu_fn(acc[4 * j + 3] + bB)),
                    pack_bf16(gelu_fn(acc[4 * j + 4] + bA), gelu_fn(acc[4 * j + 5] + bA)), pack_bf16(gelu_fn(acc[4 * j + 6] + bB), gelu_fn(acc[4 * j + 7] + bB)));
        fence_proxy_smem();
        bar_arrive(2 + wg, 160);
      }
    } else if (roleK) {
      {
        float ak[80], av[80];
        int prev = 0;
#pragma unroll 1
        for (int kb = 0; kb < 10; kb++) {
          const int s = kb % ST56; const uint32_t ph = (kb / ST56) & 1;
          mbar_wait(full56 + 8 * s, ph);
          const uint32_t sa = sb + s * SZ56 + wg * 8192, sbb = sb + s * SZ56 + 16384;
          const uint64_t da = make_desc(sa, 16, 1024, 1), db = make_desc(sbb, 4096, 512, 2);
          wg_fence();
#pragma unroll
          for (int k = 0; k < 4; k++) {
            const int sc = (kb == 0 && k == 0) ? 0 : 1;
            wgmma_n160_t01(ak, da + k * 2, db + k * 64, sc);
            wgmma_n160_t01(av, da + k * 2, db + 1280 + k * 64, sc);
          }
          wg_commit();
          if (kb > 0) { wg_wait<1>(); if (elect) release_stage(empty56 + 8 * prev); }
          prev = s;
        }
        wg_wait<0>();
        if (elect) release_stage(empty56 + 8 * prev);
        const uint32_t base0 = sb + OFF_STAGE_KV, base1 = sb + OFF_STAGE_KV2;
        {
          const uint32_t vb = ((ct < 128) ? base0 : base1) + 128 * 208 + (ct & 127) * 208;
#pragma unroll
          for (int hh = 0; hh < 4; hh++) { sts32(vb + hh * 48 + 40, 0x00003f80u); sts32(vb + hh * 48 + 44, 0u); }
        }
        mbar_wait(abar, 0);
        const float2 stA = *(const float2*)(sgen + OFF_ST + (wg * 64 + ww * 16 + g) * 8), stB = *(const float2*)(sgen + OFF_ST + (wg * 64 + ww * 16 + g + 8) * 8);
        const float* cs = (const float*)(sgen + OFF_CS) + 2 * t;
        const uint32_t rowoff = (wg * 64 + ww * 16 + g) * 208 + 4 * t;
        const uint32_t adj = (t >= 2) ? 8 : 0;
#pragma unroll
        for (int j = 0; j < 20; j++) {
          const int jj = j % 10;
          const int hb = (8 * jj) / 20;
          const bool split = (jj == 2 || jj == 7);
          const uint32_t pks = (j < 10) ? base0 : base1, vs = pks + 128 * 208;
          const uint32_t off = rowoff + (8 * jj + 4 * hb) * 2 + (split ? adj : 0);
          const float2 ck = *(const float2*)(cs + 8 * j), cv = *(const float2*)(cs + 160 + 8 * j);
          sts32(pks + off, pack_bf16(phi_fn((ak[4 * j] - stA.x * ck.x) * stA.y), phi_fn((ak[4 * j + 1] - stA.x * ck.y) * stA.y)));
          sts32(pks + off + 8 * 208, pack_bf16(phi_fn((ak[4 * j + 2] - stB.x * ck.x) * stB.y), phi_fn((ak[4 * j + 3] - stB.x * ck.y) * stB.y)));
          sts32(vs + off, pack_bf16((av[4 * j] - stA.x * cv.x) * stA.y, (av[4 * j + 1] - stA.x * cv.y) * stA.y));
          sts32(vs + off + 8 * 208, pack_bf16((av[4 * j + 2] - stB.x * cv.x) * stB.y, (av[4 * j + 3] - stB.x * cv.y) * stB.y));
        }
        bar_sync(1, 256);
        {
          const uint32_t pks = (cw < 4) ? base0 : base1, vs = pks + 128 * 208;
          const int hh = cw & 3;
          float c[2][3][4];
#pragma unroll
          for (int m = 0; m < 2; m++)
#pragma unroll
            for (int n = 0; n < 3; n++) { c[m][n][0] = c[m][n][1] = c[m][n][2] = c[m][n][3] = 0.f; }
          const int mi = lane >> 3, mr = lane & 7;
          uint32_t aa = pks + ((mi >> 1) * 8 + mr) * 208 + hh * 48 + (mi & 1) * 16;
          uint32_t ba = vs + ((mi & 1) * 8 + mr) * 208 + hh * 48 + (mi >> 1) * 16;
          uint32_t bb = vs + ((mi & 1) * 8 + mr) * 208 + hh * 48 + 32;
#pragma unroll
          for (int ks = 0; ks < 8; ks++) {
            uint32_t a[2][4], b[3][2];
            ldsm_x4_t(a[0][0], a[0][1], a[0][2], a[0][3], aa);
            ldsm_x4_t(a[1][0], a[1][1], a[1][2], a[1][3], aa + 32);
            ldsm_x4_t(b[0][0], b[0][1], b[1][0], b[1][1], ba);
            ldsm_x2_t(b[2][0], b[2][1], bb);
#pragma unroll
            for (int m = 0; m < 2; m++)
#pragma unroll
              for (int n = 0; n < 3; n++) mma_16816(c[m][n], a[m][0], a[m][1], a[m][2], a[m][3], b[n][0], b[n][1]);
            aa += 16 * 208; ba += 16 * 208; bb += 16 * 208;
          }
          float* dst = g_kvp + (size_t)(f_dj * 8 + cw) * 480 + g * 24 + 2 * t;
#pragma unroll
          for (int n = 0; n < 3; n++) {
            red_add_v2(dst + n * 8, c[0][n][0], c[0][n][1]);
            red_add_v2(dst + 8 * 24 + n * 8, c[0][n][2], c[0][n][3]);
            if (g < 4) red_add_v2(dst + 16 * 24 + n * 8, c[1][n][0], c[1][n][1]);
          }
        }
        bar_arrive(5, 288);
      }
      {
        const int mi = lane >> 3, mr = lane & 7;
        const int row = ww * 16 + (mi & 1) * 8 + mr;
        const int sw = (row >> 1) & 3;
        const uint32_t stgw = stg + wg * 20480;
        float acc[80];
        mbar_wait(qbar + 8 * wg, 0);
#pragma unroll
        for (int j = 0; j < 20; j += 2) {
          uint32_t x0, x1, x2, x3;
          ldsm_x4(x0, x1, x2, x3, sb + OFF_QT + wg * 20480 + (j >> 2) * 4096 + row * 64 + ((((j & 3) + (mi >> 1)) ^ sw) << 4));
          acc[4 * j] = phi_fn(bf_lo(x0)); acc[4 * j + 1] = phi_fn(bf_hi(x0)); acc[4 * j + 2] = phi_fn(bf_lo(x1)); acc[4 * j + 3] = phi_fn(bf_hi(x1));
          acc[4 * j + 4] = phi_fn(bf_lo(x2)); acc[4 * j + 5] = phi_fn(bf_hi(x2)); acc[4 * j + 6] = phi_fn(bf_lo(x3)); acc[4 * j + 7] = phi_fn(bf_hi(x3));
        }
        mbar_wait(zbar, 0);
        {
          const float* kvf = (const float*)(sgen + OFF_KVF);
          if (ct < 160) ((float*)(sgen + OFF_ZS))[ct] = kvf[(ct / 20) * 480 + (ct % 20) * 24 + 20];
#pragma unroll
          for (int rr = 0; rr < 6; rr++) {
            const int tl = cw + 8 * rr;
            if (tl < 44) {
              const int per = tl / 22, q = tl % 22;
              const int kk = (q < 3) ? 0 : (q < 8) ? 1 : (q < 14) ? 2 : (q < 19) ? 3 : 4;
              const int nn = (q < 3) ? q : (q < 8) ? q - 3 : (q < 14) ? q - 6 : (q < 19) ? q - 9 : q - 12;
              const int n = 8 * nn + g, hn = n / 20, en = n - 20 * hn;
              const float* kb_ = kvf + (per * 4 + hn) * 480 + en;
              float vv[4];
#pragma unroll
              for (int u = 0; u < 4; u++) {
                const int k = 16 * kk + 2 * t + (u & 1) + (u >> 1) * 8;
                const int hk = k / 20;
                vv[u] = (hk == hn) ? kb_[(k - 20 * hk) * 24] : 0.f;
              }
              *(uint2*)(sgen + OFF_TAB + tl * 256 + lane * 8) = make_uint2(pack_bf16(vv[0], vv[1]), pack_bf16(vv[2], vv[3]));
            }
          }
          bar_sync(1, 256);
        }
        const float* zs = (const float*)(sgen + OFF_ZS);
#pragma unroll
        for (int pr = 0; pr < 4; pr++) {
          float dA0 = 0.f, dA1 = 0.f, dB0 = 0.f, dB1 = 0.f;
#pragma unroll
          for (int jj = 0; jj < 5; jj++) {
            const int j = pr * 5 + jj;
            const float2 z = *(const float2*)(zs + 8 * j + 2 * t);
            const float sA = acc[4 * j] * z.x + acc[4 * j + 1] * z.y;
            const float sB = acc[4 * j + 2] * z.x + acc[4 * j + 3] * z.y;
            if (jj < 2) { dA0 += sA; dB0 += sB; }
            else if (jj > 2) { dA1 += sA; dB1 += sB; }
            else { if (t < 2) { dA0 += sA; dB0 += sB; } else { dA1 += sA; dB1 += sB; } }
          }
#pragma unroll
          for (int o = 1; o < 4; o <<= 1) {
            dA0 += __shfl_xor_sync(0xffffffffu, dA0, o); dA1 += __shfl_xor_sync(0xffffffffu, dA1, o);
            dB0 += __shfl_xor_sync(0xffffffffu, dB0, o); dB1 += __shfl_xor_sync(0xffffffffu, dB1, o);
          }
          const float iA0 = __fdividef(1.f, dA0 + 1e-6f), iA1 = __fdividef(1.f, dA1 + 1e-6f), iB0 = __fdividef(1.f, dB0 + 1e-6f), iB1 = __fdividef(1.f, dB1 + 1e-6f);
#pragma unroll
          for (int jj = 0; jj < 5; jj++) {
            const int j = pr * 5 + jj;
            const float sA = (jj < 2) ? iA0 : (jj > 2) ? iA1 : (t < 2 ? iA0 : iA1);
            const float sB = (jj < 2) ? iB0 : (jj > 2) ? iB1 : (t < 2 ? iB0 : iB1);
            acc[4 * j] *= sA; acc[4 * j + 1] *= sA; acc[4 * j + 2] *= sB; acc[4 * j + 3] *= sB;
          }
        }
        {
          float o[80];
#pragma unroll
          for (int i = 0; i < 80; i++) o[i] = 0.f;
          const uint32_t tab = sb + OFF_TAB + lane * 8;
#pragma unroll
          for (int per = 0; per < 2; per++) {
#pragma unroll
            for (int kk = 0; kk < 5; kk++) {
              const int j0 = (per * 5 + kk) * 2;
              const uint32_t a0 = pack_bf16(acc[4 * j0], acc[4 * j0 + 1]), a1 = pack_bf16(acc[4 * j0 + 2], acc[4 * j0 + 3]);
              const uint32_t a2 = pack_bf16(acc[4 * j0 + 4], acc[4 * j0 + 5]), a3 = pack_bf16(acc[4 * j0 + 6], acc[4 * j0 + 7]);
              const int q0 = (kk == 0) ? 0 : (kk == 1) ? 3 : (kk == 2) ? 8 : (kk == 3) ? 14 : 19;
              const int n0 = (kk == 0) ? 0 : (kk == 1) ? 0 : (kk == 2) ? 2 : (kk == 3) ? 5 : 7;
              const int cnt = (kk == 0) ? 3 : (kk == 1) ? 5 : (kk == 2) ? 6 : (kk == 3) ? 5 : 3;
#pragma unroll
              for (int u = 0; u < cnt; u++) {
                const uint2 b = lds64(tab + (per * 22 + q0 + u) * 256);
                const int on = per * 10 + n0 + u;
                asm volatile("mma.sync.aligned.m16n8k16.row.col.f32.bf16.bf16.f32 {%0,%1,%2,%3}, {%4,%5,%6,%7}, {%8,%9}, {%0,%1,%2,%3};"
                             : "+f"(o[4 * on]), "+f"(o[4 * on + 1]), "+f"(o[4 * on + 2]), "+f"(o[4 * on + 3]) : "r"(a0), "r"(a1), "r"(a2), "r"(a3), "r"(b.x), "r"(b.y));
              }
            }
          }
          dump_rowmajor(o, stgw, ww, lane);
        }
        fence_proxy_smem();
        bar_arrive(2 + wg, 160);
        bar_sync(7 + wg, 128);
        if (ct < 5 || (ct >= 128 && ct < 133)) release_stage(empty36 + 8 * (ct & 127));
      }
    } else if (pair == 64 && rank == 0) {
      if (ct < 4) wait_cnt(&g_cnt[C_KV + ct], 16);
      if (ct == 4) wait_cnt(&g_cnt[C_CSD], 128);
      bar_sync(1, 256);
      for (int i = ct; i < 4 * 3 * D_; i += 256) g_csum[i] = 0.f;
    }
    if (fin) {
      float acc[80];
      const int tile = f_si * 4 + f_dj;
      float4* part = (float4*)g_part + (size_t)tile * 20 * 256 + ct;
      if (!roleK) {
        mainloop36<0>(acc, 27 - XB, r, ST36, sb, wg, true, elect, true);
#pragma unroll
        for (int i = 0; i < 20; i++) __stcg(part + i * 256, make_float4(acc[4 * i], acc[4 * i + 1], acc[4 * i + 2], acc[4 * i + 3]));
        bar_sync(1, 256);
        if (ct == 0) signal_cnt(&g_cnt[C_Y + tile]);
      } else {
        const int rowA = f_si * 128 + wg * 64 + ww * 16 + g;
        const float bA = __bfloat162float(p.b2[rowA]), bB = __bfloat162float(p.b2[rowA + 8]);
        mainloop36<2>(acc, 10, r, ST36, sb, wg, true, elect);
        mainloop36<0>(acc, XB, r, ST36, sb, wg, false, elect, true);
        if (ct == 0) wait_cnt(&g_cnt[C_Y + tile], 1);
        bar_sync(1, 256);
        {
          float4 v[20];
#pragma unroll
          for (int i = 0; i < 20; i++) v[i] = __ldcg(part + i * 256);
#pragma unroll
          for (int i = 0; i < 20; i++) { acc[4 * i] += v[i].x; acc[4 * i + 1] += v[i].y; acc[4 * i + 2] += v[i].z; acc[4 * i + 3] += v[i].w; }
        }
        mbar_wait(xbar + 8 * wg, 0);
        {
          const int mi = lane >> 3, mr = lane & 7;
          const int row = ww * 16 + (mi & 1) * 8 + mr;
          const int sw = (row >> 1) & 3;
          const uint32_t stgw = stg + wg * 20480;
#pragma unroll
          for (int j = 0; j < 20; j += 2) {
            const uint32_t addr = stgw + (j >> 2) * 4096 + row * 64 + ((((j & 3) + (mi >> 1)) ^ sw) << 4);
            uint32_t x0, x1, x2, x3;
            ldsm_x4(x0, x1, x2, x3, addr);
            stsm_x4(addr, pack_bf16(acc[4 * j] + bf_lo(x0) + bA, acc[4 * j + 1] + bf_hi(x0) + bA), pack_bf16(acc[4 * j + 2] + bf_lo(x1) + bB, acc[4 * j + 3] + bf_hi(x1) + bB),
                    pack_bf16(acc[4 * j + 4] + bf_lo(x2) + bA, acc[4 * j + 5] + bf_hi(x2) + bA), pack_bf16(acc[4 * j + 6] + bf_lo(x3) + bB, acc[4 * j + 7] + bf_hi(x3) + bB));
          }
        }
        fence_proxy_smem();
        bar_arrive(2 + wg, 160);
      }
    }
  }
  __syncthreads();
  if (warp == 0) {
    unsigned old = 0;
    if (lane == 0) old = atomicAdd(&g_cnt[C_DONE], 1u);
    old = __shfl_sync(0xffffffffu, old, 0);
    if (old == gridDim.x - 1) {
      for (int i = lane; i < C_TOTAL; i += 32) g_cnt[i] = 0u;
    }
  }
}

typedef CUresult (*PFN_enc)(CUtensorMap*, CUtensorMapDataType, cuuint32_t, void*, const cuuint64_t*, const cuuint64_t*, const cuuint32_t*,
                            const cuuint32_t*, CUtensorMapInterleave, CUtensorMapSwizzle, CUtensorMapL2promotion, CUtensorMapFloatOOBfill);

static CUtensorMap mk2(PFN_enc enc, const void* ptr, int rows, int cols, int boxrows) {
  CUtensorMap m;
  cuuint64_t gd[2] = {(cuuint64_t)cols, (cuuint64_t)rows}; cuuint64_t gs[1] = {(cuuint64_t)cols * 2};
  cuuint32_t bd[2] = {64, (cuuint32_t)boxrows}; cuuint32_t es[2] = {1, 1};
  enc(&m, CU_TENSOR_MAP_DATA_TYPE_BFLOAT16, 2, (void*)ptr, gd, gs, bd, es, CU_TENSOR_MAP_INTERLEAVE_NONE, CU_TENSOR_MAP_SWIZZLE_128B,
      CU_TENSOR_MAP_L2_PROMOTION_L2_128B, CU_TENSOR_MAP_FLOAT_OOB_FILL_NONE);
  return m;
}
static CUtensorMap mk3(PFN_enc enc, const void* ptr, int K, int N, int groups, int rows = 64) {
  CUtensorMap m;
  cuuint64_t gd[3] = {32, (cuuint64_t)K, (cuuint64_t)N / 32}; cuuint64_t gs[2] = {(cuuint64_t)N * 2, 64};
  cuuint32_t bd[3] = {32, (cuuint32_t)rows, (cuuint32_t)groups}; cuuint32_t es[3] = {1, 1, 1};
  enc(&m, CU_TENSOR_MAP_DATA_TYPE_BFLOAT16, 3, (void*)ptr, gd, gs, bd, es, CU_TENSOR_MAP_INTERLEAVE_NONE, CU_TENSOR_MAP_SWIZZLE_64B,
      CU_TENSOR_MAP_L2_PROMOTION_L2_128B, CU_TENSOR_MAP_FLOAT_OOB_FILL_NONE);
  return m;
}

extern "C" void kernel_launch(void* const* d_in, const int* in_sizes, int n_in, void* d_out, int out_size) {
  const bf16* x = (const bf16*)d_in[0];
  const bf16* wqkv = (const bf16*)d_in[1];
  const bf16* wo = (const bf16*)d_in[2];
  const bf16* w1 = (const bf16*)d_in[4];
  const bf16* b1 = (const bf16*)d_in[5];
  const bf16* w2 = (const bf16*)d_in[6];
  const bf16* b2 = (const bf16*)d_in[7];
  static PFN_enc enc = nullptr;
  static void *a_q, *a_hT, *a_g, *a_pqn;
  if (!enc) {
    void* fn = nullptr; cudaDriverEntryPointQueryResult st;
    cudaGetDriverEntryPoint("cuTensorMapEncodeTiled", &fn, cudaEnableDefault, &st);
    enc = (PFN_enc)fn;
    cudaGetSymbolAddress(&a_hT, g_hT); cudaGetSymbolAddress(&a_q, g_q); cudaGetSymbolAddress(&a_g, g_g);
    cudaGetSymbolAddress(&a_pqn, g_pqn);
    cudaFuncSetAttribute(mega_kernel, cudaFuncAttributeMaxDynamicSharedMemorySize, SMEM_BYTES);
  }
  CUtensorMap tm_xn = mk2(enc, x, S_, D_, 128);
  CUtensorMap tm_w5 = mk3(enc, wqkv, D_, 3 * D_, 5);
  CUtensorMap tm_w1g = mk3(enc, wqkv, D_, 3 * D_, 1);
  CUtensorMap tm_w1 = mk2(enc, w1, S_, F_, 64);
  CUtensorMap tm_hT = mk2(enc, a_hT, D_, S_, 80);
  CUtensorMap tm_w2 = mk2(enc, w2, F_, S_, 64);
  CUtensorMap tm_g = mk2(enc, a_g, D_, F_, 80);
  CUtensorMap tm_pqn = mk2(enc, a_pqn, S_, D_, 128);
  CUtensorMap tm_MT = mk3(enc, wo, D_, D_, 1);
  CUtensorMap tm_pqs = mk3(enc, a_pqn, S_, D_, 5, 64);
  CUtensorMap tm_out = mk3(enc, d_out, S_, D_, 5, 64);
  CUtensorMap tm_xt = mk3(enc, x, S_, D_, 5, 64);
  CUtensorMap tm_qs = mk3(enc, a_q, S_, D_, 5, 64);
  Ptrs p; p.wqkv = wqkv; p.x = x; p.wo = wo; p.b1 = b1; p.b2 = b2; p.out = (bf16*)d_out; p.w1 = w1; p.w2 = w2;
  cudaLaunchConfig_t cfg = {};
  cfg.gridDim = dim3(132); cfg.blockDim = dim3(384); cfg.dynamicSmemBytes = SMEM_BYTES; cfg.stream = cudaStreamPerThread;
  cudaLaunchAttribute at[1];
  at[0].id = cudaLaunchAttributeClusterDimension; at[0].val.clusterDim.x = 2; at[0].val.clusterDim.y = 1; at[0].val.clusterDim.z = 1;
  cfg.attrs = at; cfg.numAttrs = 1;
  cudaLaunchKernelEx(&cfg, mega_kernel, tm_xn, tm_w5, tm_w1g, tm_w1, tm_hT, tm_w2, tm_g, tm_pqn, tm_MT, tm_pqs, tm_out, tm_xt, tm_qs, p);
}
```
